```python
import torch

def _softmax(x, axis=-1):
    return torch.softmax(x, dim=axis)
def _gelu(x):
    return torch.nn.functional.gelu(x, approximate="tanh")
def _silu(x):
    return torch.nn.functional.silu(x)
def _sigmoid(x):
    return torch.sigmoid(x)
def _layernorm(x, axis=-1, eps=1e-5):
    m = x.mean(dim=axis, keepdim=True)
    v = x.var(dim=axis, keepdim=True, unbiased=False)
    return (x - m) / torch.sqrt(v + eps)
def _scatter_add(tgt, idx, src, axis=0):
    return tgt.clone().index_add_(axis, idx, src)
def _segment_sum(src, seg, n):
    out = torch.zeros((n,) + src.shape[1:], dtype=src.dtype)
    return out.index_add_(0, seg, src)
def _pad(x, pw):
    flat = tuple(v for pair in reversed(pw) for v in pair)
    return torch.nn.functional.pad(x, flat)

kernel_name = 'sequential_preLN__grouped_kv_mqa__dense_activation_silu__prompt'

def setup_inputs():

    _w = (lambda a: (lambda t: t.to(torch.bfloat16) if t.is_floating_point() else t)(torch.as_tensor(a)))
    def _A_setup():
        B, S, D, H = 1, 2048, 576, 32
        Dh = D // H
        return {
            "x": _w((lambda *s: torch.randn(*s, dtype=torch.bfloat16) * 0.05)(B, S, D)),
            "wq": _w((lambda *s: torch.randn(*s, dtype=torch.bfloat16) * 0.05)(D, H * Dh)),
            "wk": _w((lambda *s: torch.randn(*s, dtype=torch.bfloat16) * 0.05)(D, Dh)),
            "wv": _w((lambda *s: torch.randn(*s, dtype=torch.bfloat16) * 0.05)(D, Dh)),
            "wo": _w((lambda *s: torch.randn(*s, dtype=torch.bfloat16) * 0.05)(H * Dh, D)),
        }
    _A_in = _A_setup()

    def _B_setup():
        B, S, D, F = 1, 2048, 576, 4608
        return {
            "x": _w((lambda *s: torch.randn(*s, dtype=torch.bfloat16) * 0.05)(B, S, D)),
            "w1": _w((lambda *s: torch.randn(*s, dtype=torch.bfloat16) * 1.6)(D, F) * (D ** -0.5)),
            "w2": _w((lambda *s: torch.randn(*s, dtype=torch.bfloat16) * 0.2)(F, D) * (F ** -0.5)),
        }
    _B_in = _B_setup()

    return {
        "A_x": _A_in["x"],
        "A_wq": _A_in["wq"],
        "A_wk": _A_in["wk"],
        "A_wv": _A_in["wv"],
        "A_wo": _A_in["wo"],
        "B_x": _B_in["x"],
        "B_w1": _B_in["w1"],
        "B_w2": _B_in["w2"],
    }

def reference(A_x, A_wq, A_wk, A_wv, A_wo, B_x, B_w1, B_w2):
    def _A_ref(x, wq, wk, wv, wo):
        B, S, D = x.shape
        H = 32
        Dh = D // H
        q = (lambda x, *d: x.permute(*d))((x @ wq).reshape(B, S, H, Dh), 0, 2, 1, 3)
        k = x @ wk
        v = x @ wv
        scores = torch.einsum("bhqd,bkd->bhqk", q, k) * (Dh ** -0.5)
        p = _softmax(scores, axis=-1)
        o = torch.einsum("bhqk,bkd->bhqd", p, v)
        return (lambda x, *d: x.permute(*d))(o, 0, 2, 1, 3).reshape(B, S, H * Dh) @ wo

    def _B_ref(x, w1, w2):
        h = torch.einsum("bsd,df->bsf", x, w1)
        h = _silu(h)
        out = torch.einsum("bsf,fd->bsd", h, w2)
        return out

    x = A_x
    h = x + _A_ref(_layernorm(x, axis=-1), A_wq, A_wk, A_wv, A_wo)
    h2 = h + _B_ref(_layernorm(h, axis=-1), B_w1, B_w2)
    return h2
```

```cpp
#include <cuda_runtime.h>
#include <cuda_bf16.h>
#include <cuda.h>
#include <stdint.h>

namespace {

#define ACT_TANH 1
#define NSLEEP 100
#define GPOS 2
#define UNIF 0
#define PJU1 3
#define PJU3 1
#define SPLIT 1
#define USE_PDL 1
constexpr int S_TOK = 2048, DM = 576, FF = 4608;
typedef __nv_bfloat16 bf16;

template<int TB> __device__ __forceinline__ void wgmma_n128_ss(float (&d)[64], uint64_t da, uint64_t db, int sc) {
  asm volatile("{\n.reg .pred p;\nsetp.ne.b32 p, %66, 0;\n"
    "wgmma.mma_async.sync.aligned.m64n128k16.f32.bf16.bf16 {%0, %1, %2, %3, %4, %5, %6, %7, %8, %9, %10, %11, %12, %13, %14, %15, %16, %17, %18, %19, %20, %21, %22, %23, %24, %25, %26, %27, %28, %29, %30, %31, %32, %33, %34, %35, %36, %37, %38, %39, %40, %41, %42, %43, %44, %45, %46, %47, %48, %49, %50, %51, %52, %53, %54, %55, %56, %57, %58, %59, %60, %61, %62, %63}, %64, %65, p, 1, 1, 0, %67;\n}\n"
    : "+f"(d[0]), "+f"(d[1]), "+f"(d[2]), "+f"(d[3]), "+f"(d[4]), "+f"(d[5]), "+f"(d[6]), "+f"(d[7]), "+f"(d[8]), "+f"(d[9]), "+f"(d[10]), "+f"(d[11]), "+f"(d[12]), "+f"(d[13]), "+f"(d[14]), "+f"(d[15]), "+f"(d[16]), "+f"(d[17]), "+f"(d[18]), "+f"(d[19]), "+f"(d[20]), "+f"(d[21]), "+f"(d[22]), "+f"(d[23]), "+f"(d[24]), "+f"(d[25]), "+f"(d[26]), "+f"(d[27]), "+f"(d[28]), "+f"(d[29]), "+f"(d[30]), "+f"(d[31]), "+f"(d[32]), "+f"(d[33]), "+f"(d[34]), "+f"(d[35]), "+f"(d[36]), "+f"(d[37]), "+f"(d[38]), "+f"(d[39]), "+f"(d[40]), "+f"(d[41]), "+f"(d[42]), "+f"(d[43]), "+f"(d[44]), "+f"(d[45]), "+f"(d[46]), "+f"(d[47]), "+f"(d[48]), "+f"(d[49]), "+f"(d[50]), "+f"(d[51]), "+f"(d[52]), "+f"(d[53]), "+f"(d[54]), "+f"(d[55]), "+f"(d[56]), "+f"(d[57]), "+f"(d[58]), "+f"(d[59]), "+f"(d[60]), "+f"(d[61]), "+f"(d[62]), "+f"(d[63])
    : "l"(da), "l"(db), "r"(sc), "n"(TB));
}
template<int TB> __device__ __forceinline__ void wgmma_n64_ss(float (&d)[32], uint64_t da, uint64_t db, int sc) {
  asm volatile("{\n.reg .pred p;\nsetp.ne.b32 p, %34, 0;\n"
    "wgmma.mma_async.sync.aligned.m64n64k16.f32.bf16.bf16 {%0, %1, %2, %3, %4, %5, %6, %7, %8, %9, %10, %11, %12, %13, %14, %15, %16, %17, %18, %19, %20, %21, %22, %23, %24, %25, %26, %27, %28, %29, %30, %31}, %32, %33, p, 1, 1, 0, %35;\n}\n"
    : "+f"(d[0]), "+f"(d[1]), "+f"(d[2]), "+f"(d[3]), "+f"(d[4]), "+f"(d[5]), "+f"(d[6]), "+f"(d[7]), "+f"(d[8]), "+f"(d[9]), "+f"(d[10]), "+f"(d[11]), "+f"(d[12]), "+f"(d[13]), "+f"(d[14]), "+f"(d[15]), "+f"(d[16]), "+f"(d[17]), "+f"(d[18]), "+f"(d[19]), "+f"(d[20]), "+f"(d[21]), "+f"(d[22]), "+f"(d[23]), "+f"(d[24]), "+f"(d[25]), "+f"(d[26]), "+f"(d[27]), "+f"(d[28]), "+f"(d[29]), "+f"(d[30]), "+f"(d[31])
    : "l"(da), "l"(db), "r"(sc), "n"(TB));
}
template<int TB> __device__ __forceinline__ void wgmma_n40_ss(float (&d)[20], uint64_t da, uint64_t db, int sc) {
  asm volatile("{\n.reg .pred p;\nsetp.ne.b32 p, %22, 0;\n"
    "wgmma.mma_async.sync.aligned.m64n40k16.f32.bf16.bf16 {%0, %1, %2, %3, %4, %5, %6, %7, %8, %9, %10, %11, %12, %13, %14, %15, %16, %17, %18, %19}, %20, %21, p, 1, 1, 0, %23;\n}\n"
    : "+f"(d[0]), "+f"(d[1]), "+f"(d[2]), "+f"(d[3]), "+f"(d[4]), "+f"(d[5]), "+f"(d[6]), "+f"(d[7]), "+f"(d[8]), "+f"(d[9]), "+f"(d[10]), "+f"(d[11]), "+f"(d[12]), "+f"(d[13]), "+f"(d[14]), "+f"(d[15]), "+f"(d[16]), "+f"(d[17]), "+f"(d[18]), "+f"(d[19])
    : "l"(da), "l"(db), "r"(sc), "n"(TB));
}
template<int TB> __device__ __forceinline__ void wgmma_n16_ss(float (&d)[8], uint64_t da, uint64_t db, int sc) {
  asm volatile("{\n.reg .pred p;\nsetp.ne.b32 p, %10, 0;\n"
    "wgmma.mma_async.sync.aligned.m64n16k16.f32.bf16.bf16 {%0, %1, %2, %3, %4, %5, %6, %7}, %8, %9, p, 1, 1, 0, %11;\n}\n"
    : "+f"(d[0]), "+f"(d[1]), "+f"(d[2]), "+f"(d[3]), "+f"(d[4]), "+f"(d[5]), "+f"(d[6]), "+f"(d[7])
    : "l"(da), "l"(db), "r"(sc), "n"(TB));
}
template<int TB> __device__ __forceinline__ void wgmma_n64_rs(float (&d)[32], uint32_t a0, uint32_t a1, uint32_t a2, uint32_t a3, uint64_t db, int sc) {
  asm volatile("{\n.reg .pred p;\nsetp.ne.b32 p, %37, 0;\n"
    "wgmma.mma_async.sync.aligned.m64n64k16.f32.bf16.bf16 {%0, %1, %2, %3, %4, %5, %6, %7, %8, %9, %10, %11, %12, %13, %14, %15, %16, %17, %18, %19, %20, %21, %22, %23, %24, %25, %26, %27, %28, %29, %30, %31}, {%32, %33, %34, %35}, %36, p, 1, 1, %38;\n}\n"
    : "+f"(d[0]), "+f"(d[1]), "+f"(d[2]), "+f"(d[3]), "+f"(d[4]), "+f"(d[5]), "+f"(d[6]), "+f"(d[7]), "+f"(d[8]), "+f"(d[9]), "+f"(d[10]), "+f"(d[11]), "+f"(d[12]), "+f"(d[13]), "+f"(d[14]), "+f"(d[15]), "+f"(d[16]), "+f"(d[17]), "+f"(d[18]), "+f"(d[19]), "+f"(d[20]), "+f"(d[21]), "+f"(d[22]), "+f"(d[23]), "+f"(d[24]), "+f"(d[25]), "+f"(d[26]), "+f"(d[27]), "+f"(d[28]), "+f"(d[29]), "+f"(d[30]), "+f"(d[31])
    : "r"(a0), "r"(a1), "r"(a2), "r"(a3), "l"(db), "r"(sc), "n"(TB));
}
template<int TB> __device__ __forceinline__ void wgmma_n128_rs(float (&d)[64], uint32_t a0, uint32_t a1, uint32_t a2, uint32_t a3, uint64_t db, int sc) {
  asm volatile("{\n.reg .pred p;\nsetp.ne.b32 p, %69, 0;\n"
    "wgmma.mma_async.sync.aligned.m64n128k16.f32.bf16.bf16 {%0, %1, %2, %3, %4, %5, %6, %7, %8, %9, %10, %11, %12, %13, %14, %15, %16, %17, %18, %19, %20, %21, %22, %23, %24, %25, %26, %27, %28, %29, %30, %31, %32, %33, %34, %35, %36, %37, %38, %39, %40, %41, %42, %43, %44, %45, %46, %47, %48, %49, %50, %51, %52, %53, %54, %55, %56, %57, %58, %59, %60, %61, %62, %63}, {%64, %65, %66, %67}, %68, p, 1, 1, %70;\n}\n"
    : "+f"(d[0]), "+f"(d[1]), "+f"(d[2]), "+f"(d[3]), "+f"(d[4]), "+f"(d[5]), "+f"(d[6]), "+f"(d[7]), "+f"(d[8]), "+f"(d[9]), "+f"(d[10]), "+f"(d[11]), "+f"(d[12]), "+f"(d[13]), "+f"(d[14]), "+f"(d[15]), "+f"(d[16]), "+f"(d[17]), "+f"(d[18]), "+f"(d[19]), "+f"(d[20]), "+f"(d[21]), "+f"(d[22]), "+f"(d[23]), "+f"(d[24]), "+f"(d[25]), "+f"(d[26]), "+f"(d[27]), "+f"(d[28]), "+f"(d[29]), "+f"(d[30]), "+f"(d[31]), "+f"(d[32]), "+f"(d[33]), "+f"(d[34]), "+f"(d[35]), "+f"(d[36]), "+f"(d[37]), "+f"(d[38]), "+f"(d[39]), "+f"(d[40]), "+f"(d[41]), "+f"(d[42]), "+f"(d[43]), "+f"(d[44]), "+f"(d[45]), "+f"(d[46]), "+f"(d[47]), "+f"(d[48]), "+f"(d[49]), "+f"(d[50]), "+f"(d[51]), "+f"(d[52]), "+f"(d[53]), "+f"(d[54]), "+f"(d[55]), "+f"(d[56]), "+f"(d[57]), "+f"(d[58]), "+f"(d[59]), "+f"(d[60]), "+f"(d[61]), "+f"(d[62]), "+f"(d[63])
    : "r"(a0), "r"(a1), "r"(a2), "r"(a3), "l"(db), "r"(sc), "n"(TB));
}
template<int TB> __device__ __forceinline__ void wgmma_n24_rs(float (&d)[12], uint32_t a0, uint32_t a1, uint32_t a2, uint32_t a3, uint64_t db, int sc) {
  asm volatile("{\n.reg .pred p;\nsetp.ne.b32 p, %17, 0;\n"
    "wgmma.mma_async.sync.aligned.m64n24k16.f32.bf16.bf16 {%0, %1, %2, %3, %4, %5, %6, %7, %8, %9, %10, %11}, {%12, %13, %14, %15}, %16, p, 1, 1, %18;\n}\n"
    : "+f"(d[0]), "+f"(d[1]), "+f"(d[2]), "+f"(d[3]), "+f"(d[4]), "+f"(d[5]), "+f"(d[6]), "+f"(d[7]), "+f"(d[8]), "+f"(d[9]), "+f"(d[10]), "+f"(d[11])
    : "r"(a0), "r"(a1), "r"(a2), "r"(a3), "l"(db), "r"(sc), "n"(TB));
}

__device__ __forceinline__ void wg_fence(){ asm volatile("wgmma.fence.sync.aligned;" ::: "memory"); }
__device__ __forceinline__ void wg_commit(){ asm volatile("wgmma.commit_group.sync.aligned;" ::: "memory"); }
template<int N> __device__ __forceinline__ void wg_wait(){ asm volatile("wgmma.wait_group.sync.aligned %0;" :: "n"(N) : "memory"); }
template<int N> __device__ __forceinline__ void fence_regs(float (&a)[N]){
  #pragma unroll
  for(int i=0;i<N;i++) asm volatile("":"+f"(a[i])::"memory");
}
__device__ __forceinline__ uint64_t mk_desc(uint32_t lo, uint32_t hi){ uint64_t d; asm("mov.b64 %0, {%1, %2};":"=l"(d):"r"(lo),"r"(hi)); return d; }
template<int D> __device__ __forceinline__ uint64_t desc_add(uint64_t d){ uint64_t r; asm("add.u64 %0, %1, %2;":"=l"(r):"l"(d),"n"(D)); return r; }
__device__ __forceinline__ uint32_t desc_addr(uint32_t saddr){ return (saddr & 0x3FFFFu) >> 4; }
constexpr uint32_t HI_SW128 = (1024/16) | (1u<<30);
__device__ __forceinline__ void mbar_init(uint32_t b, int c){ asm volatile("mbarrier.init.shared::cta.b64 [%0], %1;"::"r"(b),"r"(c)); }
__device__ __forceinline__ void mbar_expect(uint32_t b, int bytes){ asm volatile("mbarrier.arrive.expect_tx.shared::cta.b64 _, [%0], %1;"::"r"(b),"r"(bytes):"memory"); }
__device__ __forceinline__ void mbar_arrive(uint32_t b){ asm volatile("mbarrier.arrive.shared::cta.b64 _, [%0];"::"r"(b):"memory"); }
__device__ __forceinline__ void mbar_wait(uint32_t b, int ph){
  asm volatile("{.reg .pred p;\nLW: mbarrier.try_wait.parity.shared::cta.b64 p, [%0], %1;\n@!p bra LW;\n}"::"r"(b),"r"(ph):"memory"); }
__device__ __forceinline__ void mbar_fence_init(){ asm volatile("fence.mbarrier_init.release.cluster;":::"memory"); }
__device__ __forceinline__ void bar_sync(int id,int n){ asm volatile("bar.sync %0, %1;"::"r"(id),"r"(n):"memory"); }
__device__ __forceinline__ void bar_arrive(int id,int n){ asm volatile("bar.arrive %0, %1;"::"r"(id),"r"(n):"memory"); }
__device__ __forceinline__ bool bar_red_or(int id,int n,bool v){
  uint32_t r; asm volatile("{.reg .pred p,q; setp.ne.u32 q, %3, 0; bar.red.or.pred p, %1, %2, q; selp.u32 %0, 1, 0, p;}":"=r"(r):"r"(id),"r"(n),"r"((uint32_t)v):"memory"); return r!=0; }
__device__ __forceinline__ void fence_async_smem(){ asm volatile("fence.proxy.async.shared::cta;":::"memory"); }
__device__ __forceinline__ void tma2d(uint32_t dst, const CUtensorMap* tm, int c0, int c1, uint32_t bar){
  asm volatile("cp.async.bulk.tensor.2d.shared::cluster.global.mbarrier::complete_tx::bytes [%0], [%1, {%3, %4}], [%2];"
    ::"r"(dst),"l"(tm),"r"(bar),"r"(c0),"r"(c1):"memory"); }
__device__ __forceinline__ void bulk_load(uint32_t dst, const void* src, int bytes, uint32_t bar){
  asm volatile("cp.async.bulk.shared::cluster.global.mbarrier::complete_tx::bytes [%0], [%1], %2, [%3];"::"r"(dst),"l"(src),"r"(bytes),"r"(bar):"memory"); }
__device__ __forceinline__ void bulk_store(void* gdst, uint32_t ssrc, int bytes){
  asm volatile("cp.async.bulk.global.shared::cta.bulk_group [%0], [%1], %2;"::"l"(gdst),"r"(ssrc),"r"(bytes):"memory"); }
__device__ __forceinline__ void tma2d_store(const CUtensorMap* tm, uint32_t src, int c0, int c1){
  asm volatile("cp.async.bulk.tensor.2d.global.shared::cta.bulk_group [%0, {%2, %3}], [%1];"::"l"(tm),"r"(src),"r"(c0),"r"(c1):"memory"); }
__device__ __forceinline__ void bulk_commit(){ asm volatile("cp.async.bulk.commit_group;":::"memory"); }
template<int N> __device__ __forceinline__ void bulk_wait(){ asm volatile("cp.async.bulk.wait_group %0;"::"n"(N):"memory"); }
template<int N> __device__ __forceinline__ void bulk_wait_read(){ asm volatile("cp.async.bulk.wait_group.read %0;"::"n"(N):"memory"); }
__device__ __forceinline__ int fresh_tid(){ int t; asm volatile("mov.u32 %0, %%tid.x;":"=r"(t)); return t; }
__device__ __forceinline__ void pdl_wait(){ asm volatile("griddepcontrol.wait;":::"memory"); }
__device__ __forceinline__ void pdl_launch(){ asm volatile("griddepcontrol.launch_dependents;":::"memory"); }
__device__ __forceinline__ void l2_prefetch(const void* p, int bytes){ asm volatile("cp.async.bulk.prefetch.L2.global [%0], %1;"::"l"(p),"r"(bytes):"memory"); }
__device__ __forceinline__ void prefetch_tmap(const CUtensorMap* tm){ asm volatile("prefetch.tensormap [%0];"::"l"(tm):"memory"); }
__device__ __forceinline__ float ex2f(float a){ float d; asm("ex2.approx.ftz.f32 %0, %1;":"=f"(d):"f"(a)); return d;}
__device__ __forceinline__ float tanhf_fast(float a){ float d; asm("tanh.approx.f32 %0, %1;":"=f"(d):"f"(a)); return d;}
__device__ __forceinline__ float rcpf(float a){ float d; asm("rcp.approx.ftz.f32 %0, %1;":"=f"(d):"f"(a)); return d;}
__device__ __forceinline__ uint32_t pack_bf16(float lo, float hi){ uint32_t d; asm("cvt.rn.bf16x2.f32 %0, %1, %2;":"=r"(d):"f"(hi),"f"(lo)); return d;}
__device__ __forceinline__ float bf_lo(uint32_t v){ return __uint_as_float(v<<16); }
__device__ __forceinline__ float bf_hi(uint32_t v){ return __uint_as_float(v&0xFFFF0000u); }
__device__ __forceinline__ uint32_t hfma2(uint32_t a, uint32_t b, uint32_t c){ uint32_t d; asm("fma.rn.bf16x2 %0, %1, %2, %3;":"=r"(d):"r"(a),"r"(b),"r"(c)); return d;}
struct LnC { uint32_t nmh, rsh, rsl, nbl; };
__device__ __forceinline__ LnC ln_consts(float mean, float rs){
  LnC c; c.nmh=pack_bf16(-mean,-mean); c.rsh=pack_bf16(rs,rs);
  const float ml=mean+bf_lo(c.nmh), rl=rs-bf_lo(c.rsh);
  c.rsl=pack_bf16(rl,rl); c.nbl=pack_bf16(-ml*rs,-ml*rs); return c; }
__device__ __forceinline__ uint32_t ln_pair(uint32_t x, const LnC& c){
  const uint32_t d=hfma2(x,0x3F803F80u,c.nmh); return hfma2(d,c.rsh,hfma2(d,c.rsl,c.nbl)); }
__device__ __forceinline__ void sts128(uint32_t addr, uint32_t a, uint32_t b, uint32_t c, uint32_t d){
  asm volatile("st.shared.v4.b32 [%0], {%1,%2,%3,%4};"::"r"(addr),"r"(a),"r"(b),"r"(c),"r"(d):"memory"); }
__device__ __forceinline__ void sts32(uint32_t addr, uint32_t a){ asm volatile("st.shared.b32 [%0], %1;"::"r"(addr),"r"(a):"memory"); }
__device__ __forceinline__ void stmatrix_x4(uint32_t addr, uint32_t r0, uint32_t r1, uint32_t r2, uint32_t r3){
  asm volatile("stmatrix.sync.aligned.m8n8.x4.shared.b16 [%0], {%1,%2,%3,%4};"::"r"(addr),"r"(r0),"r"(r1),"r"(r2),"r"(r3):"memory"); }
__device__ __forceinline__ void pin4(uint32_t a,uint32_t b,uint32_t c,uint32_t d,uint32_t zero,uint32_t addr){
  asm volatile("{.reg .pred p; setp.ne.u32 p, %4, 0; @p st.shared.v4.b32 [%5], {%0,%1,%2,%3};}"::"r"(a),"r"(b),"r"(c),"r"(d),"r"(zero),"r"(addr):"memory"); }

constexpr int KV_TILE = 12288;
__device__ uint4    g_kv[16*KV_TILE/16];
__device__ float    g_kmax[128];
__device__ bf16     g_o[S_TOK*DM];
__device__ bf16     g_h[S_TOK*DM];
__device__ float2   g_stat[S_TOK*8];
__device__ uint4    g_part[16*9*2*8*512];
__device__ unsigned g_cnt[16*9];
__device__ unsigned g_sync[33];

#define PM(i,cond)
#define PROF_CLK(i)
#define DBG(i,cond)

#define NPOLY_ 10
constexpr int NPOLY = NPOLY_;
__host__ __device__ constexpr bool is_poly(int j){ return ((j*NPOLY)/16) != (((j+1)*NPOLY)/16); }

constexpr int PJ_STAGE = 24576;
constexpr int M_A  = 0;
constexpr int M_X  = 73728;
constexpr int M_B1 = M_X + 5*9216;
constexpr int M_B3 = M_X + 2*9216;
constexpr int M_QS = 16*KV_TILE;
constexpr int M_BAR = M_QS + 24576;
constexpr int MHA_SMEM = M_BAR + 512 + 1024;
constexpr int BAR_X=0, BAR_W=8, BAR_FREE=40, BAR_KV=48, BAR_O=176, BAR_W3=184, BAR_E3=224, SM_KMAX=240, BAR_O2=256;
constexpr float M_LIMIT = 55.f;

__device__ __forceinline__ void issue_w(uint32_t dst, uint32_t bar, const CUtensorMap* tm, int col0, int st){
  mbar_expect(bar,PJ_STAGE);
  tma2d(dst,tm,col0,st*96,bar); tma2d(dst+12288,tm,col0+64,st*96,bar);
}
template<int NBUF,int UNR> __device__ __forceinline__ void pj_main(float (&acc)[64], uint32_t sb, uint32_t bbase, uint32_t bars, const CUtensorMap* tm, int col0, bool leader, uint32_t abar0=0, uint32_t abar1=0){
  const uint32_t alo = desc_addr(sb+M_A)|(1u<<16), blo = desc_addr(bbase)|((12288/16)<<16);
  #pragma unroll UNR
  for(int st2=0;st2<3;st2++){
    if(abar0) mbar_wait(st2==0? abar0 : abar1+(st2-1)*8, 0);
    const uint64_t a0=mk_desc(__reduce_or_sync(0xffffffffu,alo+st2*(3*8192/16)),HI_SW128);
    #pragma unroll
    for(int h=0;h<2;h++){
      const int st=2*st2+h, buf=(st>=NBUF)?st-NBUF:st;
      mbar_wait(bars+buf*8,st>=NBUF);
      const uint64_t b0=mk_desc(__reduce_or_sync(0xffffffffu,blo+buf*(PJ_STAGE/16)),HI_SW128);
      wg_fence();
      #pragma unroll
      for(int i=0;i<6;i++){
        const int kq=h*6+i;
        wgmma_n128_ss<1>(acc, a0+((kq>>2)*8192+(kq&3)*32)/16, b0+i*128, (kq>0) || st2>0);
      }
      wg_commit();
      if(st>=1 && st-1+NBUF<6){ wg_wait<1>(); if(leader) issue_w(bbase+(st-1)*PJ_STAGE,bars+(st-1)*8,tm,col0,st-1+NBUF); }
    }
  }
  wg_wait<0>(); fence_regs(acc);
}
template<int N> __device__ __forceinline__ void pj_extra(float (&acc)[N/2], uint32_t sb){
  const uint64_t da=mk_desc(__reduce_or_sync(0xffffffffu,desc_addr(sb+M_A)|(1u<<16)),HI_SW128), dx=mk_desc(__reduce_or_sync(0xffffffffu,desc_addr(sb+M_X)|((128/16)<<16)),9216/16);
  wg_fence();
  #pragma unroll
  for(int kq=0;kq<36;kq++){
    if constexpr(N==40) wgmma_n40_ss<1>(acc, da+((kq>>2)*8192+(kq&3)*32)/16, dx+kq*16, kq>0);
    else                wgmma_n16_ss<1>(acc, da+((kq>>2)*8192+(kq&3)*32)/16, dx+kq*16, kq>0);
  }
  wg_commit();
}

__device__ __forceinline__ uint32_t exp2_pair(float x0, float x1, uint32_t c2, uint32_t one){
  const uint32_t w=__byte_perm(__float_as_uint(x0),__float_as_uint(x1),0x6521);
  uint32_t y; asm("lop3.b32 %0, %1, %2, %3, 0xEA;":"=r"(y):"r"(w),"r"(0x007F007Fu),"r"(one));
  uint32_t t=hfma2(y,c2,0xBC32BC32u); t=hfma2(t,y,0x3F2E3F2Eu);
  uint32_t p; asm("lop3.b32 %0, %1, %2, %3, 0xE4;":"=r"(p):"r"(w),"r"(t),"r"(0x7F807F80u));
  return p;
}
__device__ __forceinline__ void wait_counter(const unsigned* p, unsigned target){
  unsigned v, it=0;
  do { asm volatile("ld.relaxed.gpu.global.u32 %0, [%1];":"=r"(v):"l"(p):"memory"); } while(v<target && ++it<4000000u);
}
__device__ __forceinline__ void signal_counter(unsigned* p, unsigned v){ asm volatile("red.relaxed.gpu.global.add.u32 [%0], %1;"::"l"(p),"r"(v):"memory"); }
__device__ __forceinline__ float max_nan(float a, float t){ return (t>a || t!=t)?t:a; }

template<int V> struct IntC { static constexpr int value=V; };
struct MhaMaps { CUtensorMap x, wq, wo, woe, o, h, os; };

__global__ void __launch_bounds__(512,1) mha_kernel(const __grid_constant__ MhaMaps tm, const bf16* __restrict__ x,
    const bf16* __restrict__ wq, const bf16* __restrict__ wk, const bf16* __restrict__ wv, const bf16* __restrict__ wo, const bf16* __restrict__ w1, const bf16* __restrict__ w2){
  extern __shared__ uint8_t smem_raw[];
  const uint32_t sb=((uint32_t)__cvta_generic_to_shared(smem_raw)+1023)&~1023u, bars=sb+M_BAR;
  const int tid=threadIdx.x, wg=tid>>7, warp=tid>>5, w4=warp&3, lane=tid&31, ql=lane&3;
  const int b=blockIdx.x, tile=b>>2, g=b&3, col0=g*144;
  const bool agent=(tid==480);
  PM(0,agent)
  if(agent){
    #pragma unroll
    for(int i=0;i<29;i++) mbar_init(bars+i*8,(i*8==BAR_FREE)?4:1);
    mbar_init(bars+BAR_O2,1); mbar_init(bars+BAR_O2+8,1);
    mbar_fence_init();
    mbar_expect(bars+BAR_X,73728);
    #pragma unroll
    for(int i=0;i<9;i++) tma2d(sb+M_A+i*8192,&tm.x,i*64,tile*64,bars+BAR_X);
  }
  uint32_t wx[2][9]; uint4 we[3];
  {
    const uint4* wep=(const uint4*)(wq+(size_t)(tid>>1)*DM+col0+128+(tid&1)*8);
    we[0]=__ldg(wep); we[1]=__ldg(wep+256*(DM/8));
    if(tid<128) we[2]=__ldg(wep+512*(DM/8));
    #pragma unroll
    for(int p=0;p<9;p++){ wx[0][p]=0u; wx[1][p]=0u; }
    if(g<2){
      const uint32_t* wp=(const uint32_t*)(g==0?wk:wv)+tid*9;
      #pragma unroll
      for(int p=0;p<9;p++) wx[0][p]=__ldg(wp+p);
      if(tid<64){
        #pragma unroll
        for(int p=0;p<9;p++) wx[1][p]=__ldg(wp+512*9+p);
      }
    }
    __syncthreads();
    if(agent){
      #pragma unroll 1
      for(int st=0;st<4;st++) issue_w(sb+M_B1+st*PJ_STAGE,bars+BAR_W+st*8,&tm.wq,col0,st);
    }
    if(b==0 && tid<144) g_cnt[tid]=0;
  }
  PM(1,tid==64)
  mbar_wait(bars+BAR_X,0);
  PM(2,tid==64)
  {
    const int j8=lane&7, row=warp*4+(lane>>3);
    const uint32_t ra=sb+M_A+row*128+((j8^(row&7))<<4);
    uint32_t v[9][4];
    #pragma unroll
    for(int i=0;i<9;i++) asm volatile("ld.shared.v4.b32 {%0,%1,%2,%3}, [%4];":"=r"(v[i][0]),"=r"(v[i][1]),"=r"(v[i][2]),"=r"(v[i][3]):"r"(ra+i*8192));
    #pragma unroll
    for(int n=0;n<3;n++) if(n<2 || tid<128) sts128(sb+M_X+(tid&1)*9216+((tid>>1)+n*256)*16,we[n].x,we[n].y,we[n].z,we[n].w);
    #pragma unroll
    for(int n=0;n<2;n++) if(n==0 || tid<64){
      const uint32_t d=sb+M_X+2*9216+(tid+n*512)*16;
      sts128(d,wx[n][0],wx[n][1],wx[n][2],wx[n][3]); sts128(d+9216,wx[n][4],wx[n][5],wx[n][6],wx[n][7]); sts128(d+2*9216,wx[n][8],0u,0u,0u);
    }
    float s4[4]={0,0,0,0};
    #pragma unroll
    for(int i=0;i<9;i++)
      #pragma unroll
      for(int e=0;e<4;e++) s4[e]+=bf_lo(v[i][e])+bf_hi(v[i][e]);
    float s=(s4[0]+s4[1])+(s4[2]+s4[3]);
    s+=__shfl_xor_sync(~0u,s,1); s+=__shfl_xor_sync(~0u,s,2); s+=__shfl_xor_sync(~0u,s,4);
    const float mean=s*(1.f/DM); float q4[4]={0,0,0,0};
    #pragma unroll
    for(int i=0;i<9;i++)
      #pragma unroll
      for(int e=0;e<4;e++){ const float p=bf_lo(v[i][e])-mean,q=bf_hi(v[i][e])-mean; q4[e]=fmaf(p,p,fmaf(q,q,q4[e])); }
    float q=(q4[0]+q4[1])+(q4[2]+q4[3]);
    q+=__shfl_xor_sync(~0u,q,1); q+=__shfl_xor_sync(~0u,q,2); q+=__shfl_xor_sync(~0u,q,4);
    const LnC lc=ln_consts(mean,rsqrtf(q*(1.f/DM)+1e-5f));
    #pragma unroll
    for(int i=0;i<9;i++) sts128(ra+i*8192,ln_pair(v[i][0],lc),ln_pair(v[i][1],lc),ln_pair(v[i][2],lc),ln_pair(v[i][3],lc));
  }
  fence_async_smem();
  __syncthreads();
  PM(3,tid==64)
  {
    const float QS=0.34004437f;
    auto put_q=[&](int p, float a0, float a1, float a2, float a3){
      const int h=p/9, dd=p-h*9;
      const uint32_t dst=sb+M_QS+((h>>2)*6+(dd>>2)*2)*2048+((h&3)*128+w4*32+(lane&~3)+(dd&3))*4;
      sts32(dst,pack_bf16(a0*QS,a1*QS)); sts32(dst+2048,pack_bf16(a2*QS,a3*QS));
    };
    if(wg==0){
      float acc[64];
      bar_sync(7,256);
      pj_main<4,PJU1>(acc,sb,sb+M_B1,bars+BAR_W,&tm.wq,col0,tid==0);
      PM(6,tid==0)
      bar_sync(5,288);
      #pragma unroll
      for(int n=0;n<16;n++) put_q(4*n+ql,acc[4*n],acc[4*n+1],acc[4*n+2],acc[4*n+3]);
    } else if(wg==1){
      float acc[20];
      pj_extra<40>(acc,sb);
      bar_arrive(7,256);
      wg_wait<0>(); fence_regs(acc);
      if(g<2){
        float nmax=0.f;
        #pragma unroll
        for(int hrow=0;hrow<2;hrow++){
          const int kl=w4*16+(lane>>2)+hrow*8, grp=((tile&1)*64+kl)>>3;
          uint32_t u0=pack_bf16(acc[8+2*hrow],acc[9+2*hrow]), u1=pack_bf16(acc[12+2*hrow],acc[13+2*hrow]), u2=pack_bf16(acc[16+2*hrow],acc[17+2*hrow]);
          if(ql>0){
            const uint32_t fl=is_poly(grp)?0x3F80u:0u;
            if(g==0) u2=(ql==1)?(0x3F80u|(fl<<16)):((ql==2)?fl:0u);
            else     u2=(ql==1)?0x3F80u:0u;
          }
          const uint32_t dst=sb+M_X+(kl>>3)*384+(kl&7)*16+ql*4;
          sts32(dst,u0); sts32(dst+128,u1); sts32(dst+256,u2);
          float n2=bf_lo(u0)*bf_lo(u0)+bf_hi(u0)*bf_hi(u0)+bf_lo(u1)*bf_lo(u1)+bf_hi(u1)*bf_hi(u1);
          if(ql==0) n2+=bf_lo(u2)*bf_lo(u2)+bf_hi(u2)*bf_hi(u2);
          n2+=__shfl_xor_sync(~0u,n2,1); n2+=__shfl_xor_sync(~0u,n2,2);
          nmax=max_nan(nmax,n2);
        }
        #pragma unroll
        for(int o=4;o<32;o<<=1) nmax=max_nan(nmax,__shfl_xor_sync(~0u,nmax,o));
        if(lane==0) sts32(sb+M_X+3072+w4*4,__float_as_uint(nmax));
        fence_async_smem();
        bar_sync(6,128);
        PM(4,tid==128)
        if(tid==128){
          bulk_store((uint8_t*)g_kv+(tile>>1)*KV_TILE+g*6144+(tile&1)*3072,sb+M_X,3072);
          if(g==0) bulk_store(g_kmax+tile*4,sb+M_X+3072,16);
          bulk_commit(); bulk_wait<0>();
          signal_counter(&g_sync[0],1u);
        }
        PM(5,tid==128)
      }
      bar_sync(5,288);
      #pragma unroll
      for(int n=0;n<2;n++) put_q(64+4*n+ql,acc[4*n],acc[4*n+1],acc[4*n+2],acc[4*n+3]);
    } else if(warp==15){
      PM(7,agent)
      if(agent) wait_counter(&g_sync[0],64u);
      __syncwarp();
      PM(8,agent)
      const float4 km=__ldcg((const float4*)(g_kmax+lane*4));
      bar_sync(5,288);
      if(lane<2){ mbar_expect(bars+BAR_KV+lane*8,KV_TILE); bulk_load(sb+lane*KV_TILE,(const uint8_t*)g_kv+lane*KV_TILE,KV_TILE,bars+BAR_KV+lane*8); }
      float m=max_nan(max_nan(km.x,km.y),max_nan(km.z,km.w));
      #pragma unroll
      for(int o=1;o<32;o<<=1) m=max_nan(m,__shfl_xor_sync(~0u,m,o));
      if(lane==0){ sts32(bars+SM_KMAX,__float_as_uint(m)); sts32(bars+SM_KMAX+4,0u); sts32(bars+SM_KMAX+8,0u); }
    }
  }
  __syncthreads();
  PM(9,tid==64)
  {
    float kmax2; asm volatile("ld.shared.f32 %0, [%1];":"=f"(kmax2):"r"(bars+SM_KMAX));
    const uint32_t one=0x3F803F80u, c2=0x3EAB3EABu;
    uint32_t sb16=desc_addr(sb), kvbar=bars+BAR_KV;
    asm volatile("":"+r"(sb16),"+r"(kvbar));
#define OFFEXPR __reduce_or_sync(0xffffffffu,sb16+((j+rot)&15)*(KV_TILE/16))
    constexpr uint32_t kq0=(128/16)<<16, kq1=16, kvd=384+((384/16)<<16);
    constexpr uint32_t K_HI=384/16, V_HI=128/16;
    uint32_t slowmask=0;
    {
      const int tid=fresh_tid(), wg=tid>>7, ql=tid&3;
      #pragma unroll
      for(int pass=0;pass<2;pass++){
        uint32_t q[6];
        const uint32_t fa=sb+M_QS+pass*6*2048+tid*4;
        #pragma unroll
        for(int i=0;i<6;i++) asm volatile("ld.shared.b32 %0, [%1];":"=r"(q[i]):"r"(fa+i*2048));
        if(ql>0){ q[4]=0; q[5]=0; }
        float n0=bf_lo(q[0])*bf_lo(q[0])+bf_hi(q[0])*bf_hi(q[0])+bf_lo(q[2])*bf_lo(q[2])+bf_hi(q[2])*bf_hi(q[2])+bf_lo(q[4])*bf_lo(q[4])+bf_hi(q[4])*bf_hi(q[4]);
        float n1=bf_lo(q[1])*bf_lo(q[1])+bf_hi(q[1])*bf_hi(q[1])+bf_lo(q[3])*bf_lo(q[3])+bf_hi(q[3])*bf_hi(q[3])+bf_lo(q[5])*bf_lo(q[5])+bf_hi(q[5])*bf_hi(q[5]);
        n0+=__shfl_xor_sync(~0u,n0,1); n0+=__shfl_xor_sync(~0u,n0,2);
        n1+=__shfl_xor_sync(~0u,n1,1); n1+=__shfl_xor_sync(~0u,n1,2);
        const float m0=ceilf(__fsqrt_ru(n0*kmax2)*1.001f+0.01f), m1=ceilf(__fsqrt_ru(n1*kmax2)*1.001f+0.01f);
        const bool slow=bar_red_or(1+wg,128,!(m0<=M_LIMIT && m1<=M_LIMIT));
        if(!slow){
          if(ql==1){ q[4]=(__float_as_uint(-m0)>>16)|(0x43C0u<<16); q[5]=(__float_as_uint(-m1)>>16)|(0x43C0u<<16); }
          else if(ql==2){ q[4]=0xBF7Fu; q[5]=0xBF7Fu; }
        }
        sts32(fa+4*2048,q[4]); sts32(fa+5*2048,q[5]);
        slowmask|=(slow?1u:0u)<<pass;
      }
    }
    #pragma unroll 1
    for(int pass=0;pass<2;pass++){
      uint32_t qa[8]; float O[12];
      const bool slow=(slowmask>>pass)&1;
      {
        const int tid=fresh_tid();
        #pragma unroll
        for(int i=0;i<6;i++) asm volatile("ld.shared.b32 %0, [%1];":"=r"(qa[i]):"r"(sb+M_QS+(pass*6+i)*2048+tid*4));
        asm volatile("ld.shared.b32 %0, [%1];":"=r"(qa[6]):"r"(bars+SM_KMAX+4)); asm volatile("ld.shared.b32 %0, [%1];":"=r"(qa[7]):"r"(bars+SM_KMAX+8));
        if(pass==0){
          __syncthreads();
          if(tid>=480){
            mbar_wait(kvbar+8,0);
            const int i=tid-480+2;
            if(i<16){ mbar_expect(kvbar+i*8,KV_TILE); bulk_load(sb+i*KV_TILE,(const uint8_t*)g_kv+i*KV_TILE,KV_TILE,kvbar+i*8); }
          }
        } else if(tid==256){
          const int n1w=DM*FF*2/128, n0w=DM*DM*2/128;
          l2_prefetch((const uint8_t*)wo+(size_t)b*n0w,n0w);
          #pragma unroll 1
          for(int o=0;o<n1w;o+=10368){ l2_prefetch((const uint8_t*)w1+(size_t)b*n1w+o,10368); l2_prefetch((const uint8_t*)w2+(size_t)b*n1w+o,10368); }
        }
        #pragma unroll
        for(int i=0;i<12;i++) O[i]=0.f;
        fence_regs(O);
        PM(10+pass,tid==64)
      }
      auto hook=[&](int j){
        if(pass==1){
          const int tid=fresh_tid();
          if(j==10){ if((tid&127)==0) mbar_arrive(bars+BAR_FREE); }
          else if(j==12 && tid==480){
            mbar_wait(bars+BAR_FREE,0);
            #pragma unroll 1
            for(int st=0;st<4;st++) issue_w(sb+M_B3+st*PJ_STAGE,bars+BAR_W3+st*8,&tm.wo,col0,st);
            mbar_expect(bars+BAR_E3,2*9216);
            #pragma unroll 1
            for(int i=0;i<6;i++) tma2d(sb+M_X+(i/3)*9216+(i%3)*3072,&tm.woe,col0+128+(i/3)*8,(i%3)*192,bars+BAR_E3);
          }
        }
      };
      const int rot=pass*6;
      if(!slow){
        auto step=[&](uint64_t dk, uint64_t dv, auto tsel){
          constexpr uint32_t T=decltype(tsel)::value*(KV_TILE/16);
          float Sa[32], Sb[32]; uint32_t Pa[16], Pb[16];
          wg_fence();
          wgmma_n64_rs<0>(Sa,qa[0],qa[1],qa[2],qa[3],desc_add<T+kq0>(dk),0);
          wgmma_n64_rs<0>(Sa,qa[4],qa[5],qa[6],qa[7],desc_add<T+kq1>(dk),1);
          wg_commit();
          wgmma_n64_rs<0>(Sb,qa[0],qa[1],qa[2],qa[3],desc_add<T+kq0+192>(dk),0);
          wgmma_n64_rs<0>(Sb,qa[4],qa[5],qa[6],qa[7],desc_add<T+kq1+192>(dk),1);
          wg_commit();
          wg_wait<1>(); fence_regs(Sa);
          #pragma unroll
          for(int i=0;i<16;i++) Pa[i]=is_poly(i>>1)? exp2_pair(Sa[2*i],Sa[2*i+1],c2,one) : pack_bf16(ex2f(Sa[2*i]),ex2f(Sa[2*i+1]));
          wg_fence();
          wgmma_n24_rs<1>(O,Pa[0],Pa[1],Pa[2],Pa[3],desc_add<T+kvd>(dv),1);
          wgmma_n24_rs<1>(O,Pa[4],Pa[5],Pa[6],Pa[7],desc_add<T+kvd+48>(dv),1);
          wgmma_n24_rs<1>(O,Pa[8],Pa[9],Pa[10],Pa[11],desc_add<T+kvd+96>(dv),1);
          wgmma_n24_rs<1>(O,Pa[12],Pa[13],Pa[14],Pa[15],desc_add<T+kvd+144>(dv),1);
          wg_commit();
          wg_wait<1>(); fence_regs(Sb);
          #pragma unroll
          for(int i=0;i<16;i++) Pb[i]=is_poly(8+(i>>1))? exp2_pair(Sb[2*i],Sb[2*i+1],c2,one) : pack_bf16(ex2f(Sb[2*i]),ex2f(Sb[2*i+1]));
          wg_fence();
          wgmma_n24_rs<1>(O,Pb[0],Pb[1],Pb[2],Pb[3],desc_add<T+kvd+192>(dv),1);
          wgmma_n24_rs<1>(O,Pb[4],Pb[5],Pb[6],Pb[7],desc_add<T+kvd+240>(dv),1);
          wgmma_n24_rs<1>(O,Pb[8],Pb[9],Pb[10],Pb[11],desc_add<T+kvd+288>(dv),1);
          wgmma_n24_rs<1>(O,Pb[12],Pb[13],Pb[14],Pb[15],desc_add<T+kvd+336>(dv),1);
          wg_commit();
          wg_wait<0>(); fence_regs(O);
        };
        #pragma unroll 1
        for(int j=0;j<16;j+=2){
          const uint32_t off=OFFEXPR;
          const uint64_t dk=mk_desc(off,K_HI), dv=mk_desc(off,V_HI);
          if(pass==0){ mbar_wait(kvbar+j*8,0); mbar_wait(kvbar+j*8+8,0); }
          step(dk,dv,IntC<0>());
          step(dk,dv,IntC<1>());
          if((j|2)==10) hook(j+2);
        }
      } else {
        float r0=-INFINITY, r1=-INFINITY;
        #pragma unroll 1
        for(int j=0;j<16;j++){
          float S[64]; uint32_t P[32];
          const uint32_t off=OFFEXPR;
          if(pass==0) mbar_wait(kvbar+j*8,0);
          wg_fence();
          wgmma_n128_rs<0>(S,qa[0],qa[1],qa[2],qa[3],mk_desc(kq0+off,K_HI),0);
          wgmma_n128_rs<0>(S,qa[4],qa[5],qa[6],qa[7],mk_desc(kq1+off,K_HI),1);
          wg_commit();
          wg_wait<0>(); fence_regs(S);
          float t0=r0,t1=r1;
          #pragma unroll
          for(int n=0;n<16;n++){ t0=fmaxf(t0,fmaxf(S[4*n],S[4*n+1])); t1=fmaxf(t1,fmaxf(S[4*n+2],S[4*n+3])); }
          t0=fmaxf(t0,__shfl_xor_sync(~0u,t0,1)); t0=fmaxf(t0,__shfl_xor_sync(~0u,t0,2));
          t1=fmaxf(t1,__shfl_xor_sync(~0u,t1,1)); t1=fmaxf(t1,__shfl_xor_sync(~0u,t1,2));
          const float c0=ex2f(r0-t0), c1=ex2f(r1-t1);
          r0=t0; r1=t1;
          #pragma unroll
          for(int n=0;n<3;n++){ O[4*n]*=c0; O[4*n+1]*=c0; O[4*n+2]*=c1; O[4*n+3]*=c1; }
          #pragma unroll
          for(int n=0;n<16;n++){ P[2*n]=pack_bf16(ex2f(S[4*n]-r0),ex2f(S[4*n+1]-r0)); P[2*n+1]=pack_bf16(ex2f(S[4*n+2]-r1),ex2f(S[4*n+3]-r1)); }
          fence_regs(O);
          wg_fence();
          #pragma unroll
          for(int kk=0;kk<8;kk++) wgmma_n24_rs<1>(O,P[4*kk],P[4*kk+1],P[4*kk+2],P[4*kk+3],mk_desc(kvd+off+kk*48,V_HI),1);
          wg_commit();
          wg_wait<0>(); fence_regs(O);
          if((j|2)==11) hook(j+1);
        }
      }
      {
        const int tid=fresh_tid(), wg=tid>>7, w4=(tid>>5)&3, lane=tid&31, ql=tid&3;
        const float l0=__shfl_sync(~0u,O[8],(lane&~3)+1), l1=__shfl_sync(~0u,O[10],(lane&~3)+1);
        const float i0=__frcp_rn(l0), i1=__frcp_rn(l1);
        if(pass==1) __syncthreads();
        const uint32_t op=sb+M_QS+pass*12288+(w4*16+(lane>>2))*144+wg*36+ql*4;
        sts32(op,pack_bf16(O[0]*i0,O[1]*i0)); sts32(op+8*144,pack_bf16(O[2]*i1,O[3]*i1));
        sts32(op+16,pack_bf16(O[4]*i0,O[5]*i0)); sts32(op+8*144+16,pack_bf16(O[6]*i1,O[7]*i1));
        if(ql==0){ sts32(op+32,pack_bf16(O[8]*i0,O[9]*i0)); sts32(op+8*144+32,pack_bf16(O[10]*i1,O[11]*i1)); }
      }
    }
  }
  fence_async_smem();
  PM(12,threadIdx.x==64)
  __syncthreads();
  PM(13,threadIdx.x==64)
  pdl_launch();
  {
  const int tid=fresh_tid(), wg=tid>>7, warp=tid>>5, w4=warp&3, lane=tid&31, ql=lane&3;
  const bool agent=(tid==480);
  const int row0=tile*64+w4*16+(lane>>2);
  if(warp==15){
    if(agent){
      tma2d_store(&tm.os,sb+M_QS,col0,tile*64); tma2d_store(&tm.os,sb+M_QS+12288,col0+72,tile*64);
      bulk_commit();
      bulk_wait<0>();
      signal_counter(&g_sync[1+tile],1u);
      issue_w(sb+M_B3+4*PJ_STAGE,bars+BAR_W3+4*8,&tm.wo,col0,4);
      PM(14,true)
      wait_counter(&g_sync[1+tile],4u);
      PM(15,true)
      #pragma unroll
      for(int i=0;i<9;i++){
        const uint32_t ob=bars+((i<3)? BAR_O : BAR_O2+(i/3-1)*8);
        if(i%3==0) mbar_expect(ob,3*8192);
        tma2d(sb+M_A+i*8192,&tm.o,i*64,tile*64,ob);
      }
    }
    __syncwarp();
    bar_sync(8,160);
    PM(28,agent)
    if(agent){ tma2d_store(&tm.h,sb+M_B3,col0,tile*64); tma2d_store(&tm.h,sb+M_B3+8192,col0+64,tile*64); bulk_commit(); bulk_wait<0>(); }
    PM(19,agent)
  } else
  if(wg==0){
    const bf16* xp=x+(size_t)row0*DM+col0+2*ql;
    uint32_t xr[32];
    #pragma unroll
    for(int n=0;n<16;n++){ xr[2*n]=__ldg((const uint32_t*)(xp+n*8)); xr[2*n+1]=__ldg((const uint32_t*)(xp+8*DM+n*8)); }
    PM(16,tid==0)
    float acc[64];
    pj_main<5,PJU3>(acc,sb,sb+M_B3,bars+BAR_W3,&tm.wo,col0,tid==0,bars+BAR_O,bars+BAR_O2);
    PM(17,tid==0)
    uint32_t u[32];
    #pragma unroll
    for(int n=0;n<16;n++){
      u[2*n]=pack_bf16(acc[4*n]+bf_lo(xr[2*n]),acc[4*n+1]+bf_hi(xr[2*n])); u[2*n+1]=pack_bf16(acc[4*n+2]+bf_lo(xr[2*n+1]),acc[4*n+3]+bf_hi(xr[2*n+1]));
    }
    PM(26,tid==0)
    {
      const int m=lane>>3, row=w4*16+(m&1)*8+(lane&7);
      #pragma unroll
      for(int g2=0;g2<8;g2++){
        const int ch=(g2&3)*2+(m>>1);
        stmatrix_x4(sb+M_B3+(g2>>2)*8192+row*128+((ch^(row&7))<<4),u[4*g2],u[4*g2+1],u[4*g2+2],u[4*g2+3]);
      }
      fence_async_smem();
      bar_arrive(8,160);
      PM(27,tid==0)
    }
    float s0=0,s1=0;
    #pragma unroll
    for(int n=0;n<16;n++){
      acc[4*n]=bf_lo(u[2*n]); acc[4*n+1]=bf_hi(u[2*n]); acc[4*n+2]=bf_lo(u[2*n+1]); acc[4*n+3]=bf_hi(u[2*n+1]);
      s0+=acc[4*n]+acc[4*n+1]; s1+=acc[4*n+2]+acc[4*n+3];
    }
    s0+=__shfl_xor_sync(~0u,s0,1); s0+=__shfl_xor_sync(~0u,s0,2); s1+=__shfl_xor_sync(~0u,s1,1); s1+=__shfl_xor_sync(~0u,s1,2);
    const float m0=s0*(1.f/128), m1=s1*(1.f/128); float q0=0,q1=0;
    #pragma unroll
    for(int n=0;n<16;n++){ const float p=acc[4*n]-m0,q=acc[4*n+1]-m0,r=acc[4*n+2]-m1,t=acc[4*n+3]-m1; q0=fmaf(p,p,fmaf(q,q,q0)); q1=fmaf(r,r,fmaf(t,t,q1)); }
    q0+=__shfl_xor_sync(~0u,q0,1); q0+=__shfl_xor_sync(~0u,q0,2); q1+=__shfl_xor_sync(~0u,q1,1); q1+=__shfl_xor_sync(~0u,q1,2);
    if(ql==0){ g_stat[row0*8+g*2]=make_float2(m0,q0); g_stat[(row0+8)*8+g*2]=make_float2(m1,q1); }
    PM(18,tid==0)
  } else if(wg==1){
    const bf16* xp=x+(size_t)row0*DM+col0+128+2*ql;
    uint32_t xr[4];
    #pragma unroll
    for(int n=0;n<2;n++){ xr[2*n]=__ldg((const uint32_t*)(xp+n*8)); xr[2*n+1]=__ldg((const uint32_t*)(xp+8*DM+n*8)); }
    float acc[8];
    mbar_wait(bars+BAR_E3,0);
    mbar_wait(bars+BAR_O,0); mbar_wait(bars+BAR_O2,0); mbar_wait(bars+BAR_O2+8,0);
    pj_extra<16>(acc,sb);
    wg_wait<0>(); fence_regs(acc);
    bf16* hp=g_h+(size_t)row0*DM+col0+128+2*ql;
    float s0=0,s1=0;
    #pragma unroll
    for(int n=0;n<2;n++){
      const uint32_t u0=pack_bf16(acc[4*n]+bf_lo(xr[2*n]),acc[4*n+1]+bf_hi(xr[2*n])), u1=pack_bf16(acc[4*n+2]+bf_lo(xr[2*n+1]),acc[4*n+3]+bf_hi(xr[2*n+1]));
      *(uint32_t*)(hp+n*8)=u0; *(uint32_t*)(hp+8*DM+n*8)=u1;
      acc[4*n]=bf_lo(u0); acc[4*n+1]=bf_hi(u0); acc[4*n+2]=bf_lo(u1); acc[4*n+3]=bf_hi(u1);
      s0+=acc[4*n]+acc[4*n+1]; s1+=acc[4*n+2]+acc[4*n+3];
    }
    s0+=__shfl_xor_sync(~0u,s0,1); s0+=__shfl_xor_sync(~0u,s0,2); s1+=__shfl_xor_sync(~0u,s1,1); s1+=__shfl_xor_sync(~0u,s1,2);
    const float m0=s0*(1.f/16), m1=s1*(1.f/16); float q0=0,q1=0;
    #pragma unroll
    for(int n=0;n<2;n++){ const float p=acc[4*n]-m0,q=acc[4*n+1]-m0,r=acc[4*n+2]-m1,t=acc[4*n+3]-m1; q0=fmaf(p,p,fmaf(q,q,q0)); q1=fmaf(r,r,fmaf(t,t,q1)); }
    q0+=__shfl_xor_sync(~0u,q0,1); q0+=__shfl_xor_sync(~0u,q0,2); q1+=__shfl_xor_sync(~0u,q1,1); q1+=__shfl_xor_sync(~0u,q1,2);
    if(ql==0){ g_stat[row0*8+g*2+1]=make_float2(m0,q0); g_stat[(row0+8)*8+g*2+1]=make_float2(m1,q1); }
  }
  }

}

constexpr int X_BYTES=128*576*2, SLOT=24576, NSLOT=3, NS2=7;
constexpr int FFN_RING=X_BYTES, FFN_BAR=FFN_RING+NSLOT*SLOT, S2_BASE=49152;
constexpr int FFN_SMEM=FFN_BAR+512+1024;

template<int NV,int I0,int I1> __device__ __forceinline__ void silu_chunk(const float (&a)[NV], uint32_t* H, uint32_t zero, uint32_t addr){
  #pragma unroll
  for(int i=I0;i<I1;i++){
    const float u0=a[2*i],u1=a[2*i+1];
    H[i]=pack_bf16(fmaf(u0,tanhf_fast(u0),u0),fmaf(u1,tanhf_fast(u1),u1));
  }
  #pragma unroll
  for(int i=I0;i<I1;i+=4) pin4(H[i],H[i+1],H[i+2],H[i+3],zero,addr);
}
template<int P,bool CONV> __device__ __forceinline__ void pass128(float (&A)[64], float (&B)[64], uint32_t* Hprev, uint32_t bars, uint32_t ring16, uint32_t xlo, bool leader, uint32_t zero){
  const uint64_t dx=mk_desc(__reduce_or_sync(0xffffffffu,xlo),HI_SW128), dring=mk_desc(__reduce_or_sync(0xffffffffu,ring16),HI_SW128);
  #pragma unroll
  for(int s=0;s<6;s++){
    const int n=P*6+s, slot=n%NSLOT, ph=(n/NSLOT)&1;
    mbar_wait(bars+slot*8,ph);
    wg_fence();
    #pragma unroll
    for(int i=0;i<6;i++){
      const int kq=s*6+i;
      wgmma_n128_ss<1>(A,dx+((kq>>2)*16384+(kq&3)*32)/16,dring+(slot*(SLOT/16)+i*128+((12288/16)<<16)),kq>0);
      if(i==0){ wg_commit(); wg_wait<1>(); if(n>0 && leader) mbar_arrive(bars+NSLOT*8+((n+NSLOT-1)%NSLOT)*8); }
    }
    wg_commit();
    if(CONV){
      if(s==0){ fence_regs(B); silu_chunk<64,0,8>(B,Hprev,zero,bars); }
      if(s==1) silu_chunk<64,8,12>(B,Hprev,zero,bars);
      if(s==2) silu_chunk<64,12,16>(B,Hprev,zero,bars);
      if(s==3) silu_chunk<64,16,24>(B,Hprev,zero,bars);
      if(s==4) silu_chunk<64,24,28>(B,Hprev,zero,bars);
      if(s==5) silu_chunk<64,28,32>(B,Hprev,zero,bars);
    }
  }
}

__global__ void __launch_bounds__(384,1) ffn_kernel(const __grid_constant__ CUtensorMap tmW1, const __grid_constant__ CUtensorMap tmW2, const __grid_constant__ CUtensorMap tmH,
    bf16* __restrict__ out, uint32_t zero){
  extern __shared__ uint8_t smem_raw[];
  const uint32_t sb=((uint32_t)__cvta_generic_to_shared(smem_raw)+1023)&~1023u;
  const int tid=threadIdx.x, wg=__shfl_sync(0xffffffffu,tid>>7,0), warp=(tid>>5)&3, lane=tid&31;
  const int t=blockIdx.x>>3, c=blockIdx.x&7;
  PROF_CLK(2)
  PM(20,tid==0)
  const uint32_t full1=sb+FFN_BAR, empty1=full1+NSLOT*8, full2=sb+FFN_BAR+64, empty2=full2+NS2*8, xfree=empty2+NS2*8;
  const uint32_t stg_full=xfree+8, stg_empty=stg_full+32, rdy=stg_empty+32, hbar=rdy+72;
  if(tid==0){
    for(int s=0;s<NSLOT;s++){ mbar_init(full1+s*8,1); mbar_init(empty1+s*8,2); }
    for(int s=0;s<NS2;s++){ mbar_init(full2+s*8,1); mbar_init(empty2+s*8,2); }
    mbar_init(xfree,2);
    for(int s=0;s<4;s++){ mbar_init(stg_full+s*8,128); mbar_init(stg_empty+s*8,1); }
    for(int s=0;s<9;s++){ mbar_init(rdy+s*8,1); mbar_init(hbar+s*8,1); }
    mbar_fence_init();
  }
  __syncthreads();
  if(wg==2){
    asm volatile("setmaxnreg.dec.sync.aligned.u32 24;");
    if(warp==0 && lane==0){
      #pragma unroll 1
      for(int n=0;n<27;n++){
        const int slot=n%NSLOT, ph=(n/NSLOT)&1;
        mbar_wait(empty1+slot*8,ph^1);
        mbar_expect(full1+slot*8,SLOT);
        const uint32_t dst=sb+FFN_RING+slot*SLOT, bar=full1+slot*8;
        if(n<24){ const int col=c*576+(n/6)*128, row=(n%6)*96; tma2d(dst,&tmW1,col,row,bar); tma2d(dst+12288,&tmW1,col+64,row,bar); }
        else { const int s=n-24; tma2d(dst,&tmW1,c*576+512,s*192,bar); tma2d(dst+12288,&tmW1,c*576+512,s*192+96,bar); }
      }
      #pragma unroll 1
      for(int m=0;m<27;m++){
        const int a=(m+4)%NS2;
        if(m<3) mbar_wait(empty1+m*8,0);
        else if(m==3) mbar_wait(xfree,0);
        if(m>=NS2) mbar_wait(empty2+a*8,((m/NS2)-1)&1);
        mbar_expect(full2+a*8,SLOT);
        const int j=m/3, s=m%3; const uint32_t dst=sb+S2_BASE+a*SLOT;
        tma2d(dst,&tmW2,j*64,c*576+s*192,full2+a*8); tma2d(dst+12288,&tmW2,j*64,c*576+s*192+96,full2+a*8);
      }
    } else if(warp<3 && warp>0 && lane==0){
      pdl_wait();
      #pragma unroll 1
      for(int j=warp-1;j<9;j+=2){
        #pragma unroll
        for(int w=0;w<2;w++){
          mbar_wait(stg_full+(w*2+(j&1))*8,(j>>1)&1);
          bulk_store((uint8_t*)g_part+((size_t)(((t*9+j)*2+w)*8+c))*8192,sb+w*16384+(j&1)*8192,8192);
          bulk_commit();
        }
        bulk_wait_read<1>();
        mbar_arrive(stg_empty+(j&1)*8);
        bulk_wait_read<0>();
        mbar_arrive(stg_empty+(2+(j&1))*8);
        bulk_wait<0>();
        asm volatile("red.relaxed.gpu.global.add.u32 [%0], 2;"::"l"(&g_cnt[t*9+j]):"memory");
      }
    } else if(warp==3 && lane==0){
      pdl_wait();
      #pragma unroll 1
      for(int i=0;i<9;i++){ mbar_expect(hbar+i*8,16384); tma2d(sb+i*16384,&tmH,i*64,t*128,hbar+i*8); }
      if(blockIdx.x==0) for(int i=0;i<33;i++) g_sync[i]=0;
      #pragma unroll 1
      for(int j=0;j<9;j++){
        unsigned v, it=0;
        do { asm volatile("ld.relaxed.gpu.global.u32 %0, [%1];":"=r"(v):"l"(&g_cnt[t*9+j]):"memory"); } while(v<16u && ++it<2000000u && (__nanosleep(NSLEEP),true));
        mbar_arrive(rdy+j*8);
      }
    }
  } else {
    asm volatile("setmaxnreg.inc.sync.aligned.u32 240;");
    const bool leader=(tid&127)==0;
    pdl_wait();
    PM(21,tid==0)
    uint32_t H[144];
    const uint32_t xlo=desc_addr(sb+wg*8192)|(1u<<16), ring16=desc_addr(sb+FFN_RING);
    float A[64],B[64];
    {
      const int sub=lane>>3, j8=lane&7;
      LnC lc[4]; uint32_t xad[4];
      #pragma unroll
      for(int it=0;it<4;it++){
        const float2 st=__ldcg(&g_stat[(t*128+wg*64+warp*16+it*4+sub)*8+j8]);
        const float cnt=(j8&1)?16.f:128.f;
        float s=st.x*cnt; s+=__shfl_xor_sync(~0u,s,1); s+=__shfl_xor_sync(~0u,s,2); s+=__shfl_xor_sync(~0u,s,4);
        const float mean=s*(1.f/DM), d=st.x-mean;
        float q=fmaf(d*d,cnt,st.y); q+=__shfl_xor_sync(~0u,q,1); q+=__shfl_xor_sync(~0u,q,2); q+=__shfl_xor_sync(~0u,q,4);
        lc[it]=ln_consts(mean,rsqrtf(q*(1.f/DM)+1e-5f)*(ACT_TANH? 0.5f : -1.4426950408889634f));
        { const int lr=wg*64+warp*16+it*4+sub; xad[it]=sb+lr*128+((j8^(lr&7))<<4); }
      }
      #pragma unroll 1
      for(int i=0;i<9;i++){
        mbar_wait(hbar+i*8,0);
        uint32_t w4[4][4];
        #pragma unroll
        for(int it=0;it<4;it++)
          asm volatile("ld.shared.v4.b32 {%0,%1,%2,%3}, [%4];":"=r"(w4[it][0]),"=r"(w4[it][1]),"=r"(w4[it][2]),"=r"(w4[it][3]):"r"(xad[it]+i*16384));
        #pragma unroll
        for(int it=0;it<4;it++)
          sts128(xad[it]+i*16384,ln_pair(w4[it][0],lc[it]),ln_pair(w4[it][1],lc[it]),ln_pair(w4[it][2],lc[it]),ln_pair(w4[it][3],lc[it]));
      }
      fence_async_smem();
      bar_sync(1+wg,128);
    }
    PM(22,tid==0)
    pass128<0,false>(A,B,H,full1,ring16,xlo,leader,zero);
    PM(30,tid==0)
    pass128<1,true>(B,A,H,full1,ring16,xlo,leader,zero);
    PM(31,tid==0)
    pass128<2,true>(A,B,H+32,full1,ring16,xlo,leader,zero);
    pass128<3,true>(B,A,H+64,full1,ring16,xlo,leader,zero);
    float C[32];
    const uint64_t dx=mk_desc(__reduce_or_sync(0xffffffffu,xlo),HI_SW128), dring=mk_desc(__reduce_or_sync(0xffffffffu,ring16),HI_SW128);
    #pragma unroll
    for(int s=0;s<3;s++){
      const int n=24+s, slot=n%NSLOT, ph=(n/NSLOT)&1;
      mbar_wait(full1+slot*8,ph);
      wg_fence();
      #pragma unroll
      for(int i=0;i<12;i++){
        const int kq=s*12+i;
        wgmma_n64_ss<1>(C,dx+((kq>>2)*16384+(kq&3)*32)/16,dring+(slot*(SLOT/16)+i*128+(1u<<16)),kq>0);
      }
      wg_commit();
      wg_wait<1>();
      if(leader) mbar_arrive(empty1+((n+NSLOT-1)%NSLOT)*8);
      if(s==0){ fence_regs(B); silu_chunk<64,0,12>(B,H+96,zero,full1); }
      if(s==1) silu_chunk<64,12,24>(B,H+96,zero,full1);
      if(s==2) silu_chunk<64,24,32>(B,H+96,zero,full1);
    }
    wg_wait<0>(); fence_regs(C);
    if(leader){ mbar_arrive(empty1+(26%NSLOT)*8); mbar_arrive(xfree); }
    silu_chunk<32,0,16>(C,H+128,zero,full1);
    PM(23,tid==0)
    const uint32_t stg=sb+wg*16384;
    mbar_wait(xfree,0);
    if(wg==1) bar_sync(4,256);
    const uint32_t s2lo=desc_addr(sb+S2_BASE);
    const int ltid=tid&127, orow=c*16+wg*8+(ltid>>4), oq=ltid&15, orr=orow&63;
    const uint8_t* gsrc=(const uint8_t*)g_part+(size_t)((t*9*2+(c>>2))*8)*8192+orr*128+(((oq>>1)^(orr&7))<<4)+(oq&1)*8;
    const size_t ooff=(size_t)(t*128+orow)*DM+oq*4;
    uint2 gv[8], gh;
    auto gather_load=[&](int jj){
      mbar_wait(rdy+jj*8,0);
      #pragma unroll
      for(int cc=0;cc<8;cc++) gv[cc]=__ldcg((const uint2*)(gsrc+(size_t)jj*(16*8192)+cc*8192));
      gh=__ldcg((const uint2*)(g_h+ooff+jj*64));
    };
    auto gather_store=[&](int jj){
      float s0=0,s1=0,s2=0,s3=0;
      #pragma unroll
      for(int cc=0;cc<8;cc++){ s0+=bf_lo(gv[cc].x); s1+=bf_hi(gv[cc].x); s2+=bf_lo(gv[cc].y); s3+=bf_hi(gv[cc].y); }
      const float sc=ACT_TANH? 1.f : -0.6931471805599453f;
      uint2 r; r.x=pack_bf16(fmaf(s0,sc,bf_lo(gh.x)),fmaf(s1,sc,bf_hi(gh.x))); r.y=pack_bf16(fmaf(s2,sc,bf_lo(gh.y)),fmaf(s3,sc,bf_hi(gh.y)));
      *(uint2*)(out+ooff+jj*64)=r;
    };
#define GLAG 2
    constexpr int LAG=GLAG;
    int a=4, ph2=0;
    #pragma unroll 1
    for(int j=0;j<9;j++){
      float D[32];
      int aprev=0;
      #pragma unroll
      for(int s=0;s<3;s++){
        mbar_wait(full2+a*8,ph2);
        const uint64_t bb=mk_desc(__reduce_or_sync(0xffffffffu,s2lo+a*(SLOT/16)+(1u<<16)),HI_SW128);
        wg_fence();
        #pragma unroll
        for(int i=0;i<12;i++){
          const int kq=s*12+i;
          wgmma_n64_rs<1>(D,H[4*kq],H[4*kq+1],H[4*kq+2],H[4*kq+3],bb+i*128,kq>0);
        }
        wg_commit();
        if(s==GPOS){ if(j>LAG) gather_store(j-LAG-1); if(j>=LAG) gather_load(j-LAG); }
        if(s>0){ wg_wait<1>(); if(leader) mbar_arrive(empty2+aprev*8); }
        if(j==0 && s==2 && wg==0) bar_arrive(4,256);
        aprev=a; a++; if(a==NS2) a=0; if(a==4) ph2^=1;
      }
      wg_wait<0>(); fence_regs(D);
      if(leader) mbar_arrive(empty2+aprev*8);
      const uint32_t sbuf=stg+(j&1)*8192;
      if(j>=2) mbar_wait(stg_empty+(wg*2+(j&1))*8,((j>>1)-1)&1);
      #pragma unroll
      for(int g2=0;g2<4;g2++){
        const int m=lane>>3, row=warp*16+(m&1)*8+(lane&7), ch=g2*2+(m>>1);
        stmatrix_x4(sbuf+row*128+((ch^(row&7))<<4), pack_bf16(D[8*g2],D[8*g2+1]),pack_bf16(D[8*g2+2],D[8*g2+3]),pack_bf16(D[8*g2+4],D[8*g2+5]),pack_bf16(D[8*g2+6],D[8*g2+7]));
      }
      fence_async_smem();
      mbar_arrive(stg_full+(wg*2+(j&1))*8);
    }
    PM(24,tid==0)
    #pragma unroll 1
    for(int jj=9-LAG;jj<=9;jj++){ gather_store(jj-1); if(jj<9) gather_load(jj); }
    PM(25,tid==0)
    PROF_CLK(3)
  }
}

typedef CUresult (*EncodeFn)(CUtensorMap*, CUtensorMapDataType, cuuint32_t, void*, const cuuint64_t*, const cuuint64_t*, const cuuint32_t*, const cuuint32_t*,
                             CUtensorMapInterleave, CUtensorMapSwizzle, CUtensorMapL2promotion, CUtensorMapFloatOOBfill);
CUtensorMap make_map(EncodeFn enc, const void* p, uint64_t cols, uint64_t rows, uint32_t box_cols, uint32_t box_rows, CUtensorMapSwizzle sw=CU_TENSOR_MAP_SWIZZLE_128B){
  CUtensorMap m; cuuint64_t d[2]={cols,rows}, s[1]={cols*2}; cuuint32_t b[2]={box_cols,box_rows}, e[2]={1,1};
  enc(&m,CU_TENSOR_MAP_DATA_TYPE_BFLOAT16,2,(void*)p,d,s,b,e,CU_TENSOR_MAP_INTERLEAVE_NONE,sw,CU_TENSOR_MAP_L2_PROMOTION_L2_128B,CU_TENSOR_MAP_FLOAT_OOB_FILL_NONE);
  return m;
}

}

extern "C" void kernel_launch(void* const* d_in, const int* in_sizes, int n_in, void* d_out, int out_size){
  (void)in_sizes; (void)n_in; (void)out_size;
  const bf16* x =(const bf16*)d_in[0]; const bf16* wq=(const bf16*)d_in[1]; const bf16* wk=(const bf16*)d_in[2];
  const bf16* wv=(const bf16*)d_in[3]; const bf16* wo=(const bf16*)d_in[4];
  const bf16* w1=(const bf16*)d_in[6]; const bf16* w2=(const bf16*)d_in[7];
  static EncodeFn enc=nullptr; static void* o_ptr=nullptr; static void* h_ptr=nullptr;
  if(!enc){
    void* fn=nullptr; cudaDriverEntryPointQueryResult qr;
    cudaGetDriverEntryPoint("cuTensorMapEncodeTiled",&fn,cudaEnableDefault,&qr); enc=(EncodeFn)fn;
    cudaGetSymbolAddress(&o_ptr,g_o); cudaGetSymbolAddress(&h_ptr,g_h);
    cudaFuncSetAttribute(mha_kernel,cudaFuncAttributeMaxDynamicSharedMemorySize,MHA_SMEM);
    cudaFuncSetAttribute(ffn_kernel,cudaFuncAttributeMaxDynamicSharedMemorySize,FFN_SMEM);
  }
  MhaMaps mm;
  mm.x=make_map(enc,x,DM,S_TOK,64,64); mm.o=make_map(enc,o_ptr,DM,S_TOK,64,64); mm.h=make_map(enc,h_ptr,DM,S_TOK,64,64); mm.os=make_map(enc,o_ptr,DM,S_TOK,72,64,CU_TENSOR_MAP_SWIZZLE_NONE);
  mm.wq=make_map(enc,wq,DM,DM,64,96);
  mm.wo=make_map(enc,wo,DM,DM,64,96); mm.woe=make_map(enc,wo,DM,DM,8,192,CU_TENSOR_MAP_SWIZZLE_NONE);
  const CUtensorMap mW1=make_map(enc,w1,FF,DM,64,96), mW2=make_map(enc,w2,DM,FF,64,96), mH=make_map(enc,h_ptr,DM,S_TOK,64,128);
  cudaStream_t st=cudaStreamPerThread;
  cudaLaunchAttribute pdl[1]; pdl[0].id=cudaLaunchAttributeProgrammaticStreamSerialization; pdl[0].val.programmaticStreamSerializationAllowed=USE_PDL;
  cudaLaunchConfig_t cfg={}; cfg.gridDim=dim3(128); cfg.stream=st; cfg.attrs=pdl; cfg.numAttrs=1;
  mha_kernel<<<128,512,MHA_SMEM,st>>>(mm,x,wq,wk,wv,wo,w1,w2);
  cfg.blockDim=dim3(384); cfg.dynamicSmemBytes=FFN_SMEM; cudaLaunchKernelEx(&cfg,ffn_kernel,mW1,mW2,mH,(bf16*)d_out,0u);
}
```
